```python
import torch

def _softmax(x, axis=-1):
    return torch.softmax(x, dim=axis)
def _gelu(x):
    return torch.nn.functional.gelu(x, approximate="tanh")
def _silu(x):
    return torch.nn.functional.silu(x)
def _sigmoid(x):
    return torch.sigmoid(x)
def _layernorm(x, axis=-1, eps=1e-5):
    m = x.mean(dim=axis, keepdim=True)
    v = x.var(dim=axis, keepdim=True, unbiased=False)
    return (x - m) / torch.sqrt(v + eps)
def _scatter_add(tgt, idx, src, axis=0):
    return tgt.clone().index_add_(axis, idx, src)
def _segment_sum(src, seg, n):
    out = torch.zeros((n,) + src.shape[1:], dtype=src.dtype)
    return out.index_add_(0, seg, src)
def _pad(x, pw):
    flat = tuple(v for pair in reversed(pw) for v in pair)
    return torch.nn.functional.pad(x, flat)

kernel_name = 'recurrent_scan__mha_block_cached__dense_activation_silu__prompt'

def setup_inputs():

    _w = (lambda a: (lambda t: t.to(torch.bfloat16) if t.is_floating_point() else t)(torch.as_tensor(a)))
    def _A_setup():
        B, Sq, D = 1, 2048, 512
        H, Sk, Dh = 32, 2048, 128
        return {
            "x": _w((lambda *s: torch.randn(*s, dtype=torch.bfloat16) * 0.05)(B, Sq, D)),
            "k_cache": _w((lambda *s: torch.randn(*s, dtype=torch.bfloat16) * 3.2)(B, H, Sk, Dh)),
            "v_cache": _w((lambda *s: torch.randn(*s, dtype=torch.bfloat16) * 3.2)(B, H, Sk, Dh)),
            "wq": _w((lambda *s: torch.randn(*s, dtype=torch.bfloat16) * 3.2)(D, H * Dh) * (D ** -0.5)),
            "wo": _w((lambda *s: torch.randn(*s, dtype=torch.bfloat16) * 3.2)(H * Dh, D) * ((H * Dh) ** -0.5)),
        }
    _A_in = _A_setup()

    def _B_setup():
        B, S, D, F = 1, 2048, 512, 1792
        return {
            "x": _w((lambda *s: torch.randn(*s, dtype=torch.bfloat16) * 0.05)(B, S, D)),
            "w1": _w((lambda *s: torch.randn(*s, dtype=torch.bfloat16) * 3.2)(D, F) * (D ** -0.5)),
            "w2": _w((lambda *s: torch.randn(*s, dtype=torch.bfloat16) * 0.4)(F, D) * (F ** -0.5)),
        }
    _B_in = _B_setup()

    return {
        "A_x": _A_in["x"],
        "A_k_cache": _A_in["k_cache"],
        "A_v_cache": _A_in["v_cache"],
        "A_wq": _A_in["wq"],
        "A_wo": _A_in["wo"],
        "B_x": _B_in["x"],
        "B_w1": _B_in["w1"],
        "B_w2": _B_in["w2"],
    }

def reference(A_x, A_k_cache, A_v_cache, A_wq, A_wo, B_x, B_w1, B_w2):
    def _A_ref(x, k_cache, v_cache, wq, wo):
        B, Sq, D = x.shape
        H, Dh = 32, 128
        q = (lambda x, *d: x.permute(*d))((x @ wq).reshape(B, Sq, H, Dh), 0, 2, 1, 3)
        scores = torch.einsum("bhqd,bhkd->bhqk", q, k_cache) * (Dh ** -0.5)
        p = _softmax(scores, axis=-1)
        o = torch.einsum("bhqk,bhkd->bhqd", p, v_cache)
        return (lambda x, *d: x.permute(*d))(o, 0, 2, 1, 3).reshape(B, Sq, H * Dh) @ wo

    def _B_ref(x, w1, w2):
        h = torch.einsum("bsd,df->bsf", x, w1)
        h = _silu(h)
        out = torch.einsum("bsf,fd->bsd", h, w2)
        return out

    x = A_x
    xn = _layernorm(x, axis=-1)
    s = _A_ref(xn, A_k_cache, A_v_cache, A_wq, A_wo)
    g = _silu(_B_ref(xn, B_w1, B_w2))
    return x + s * g
```

```cpp
#include <cuda_runtime.h>
#include <cuda_bf16.h>
#include <cuda.h>
#include <stdint.h>

#define DEVINL __device__ __forceinline__

constexpr int SEQ = 2048, DM = 512, NH = 32, DH = 128, FF = 1792;
constexpr int CLUSTER = 2;
constexpr int NSLOT = 7;
constexpr int SLOT_BYTES = 32768;
constexpr int NTHREADS = 384;
constexpr int SMEM_BYTES = NSLOT * SLOT_BYTES + 1024   + 256  ;

__device__ __nv_bfloat16 g_xn[SEQ * DM];
__device__ float g_sacc[SEQ * DM];
__device__ float g_facc[SEQ * DM];

DEVINL uint32_t smem_u32(const void* p) { return (uint32_t)__cvta_generic_to_shared(p); }

DEVINL void mbar_init(uint32_t bar, uint32_t count) {
    asm volatile("mbarrier.init.shared::cta.b64 [%0], %1;" :: "r"(bar), "r"(count) : "memory");
}
DEVINL void mbar_expect_tx(uint32_t bar, uint32_t bytes) {
    asm volatile("mbarrier.arrive.expect_tx.shared::cta.b64 _, [%0], %1;" :: "r"(bar), "r"(bytes) : "memory");
}
DEVINL void mbar_arrive(uint32_t bar) {
    asm volatile("mbarrier.arrive.shared::cta.b64 _, [%0];" :: "r"(bar) : "memory");
}
DEVINL void mbar_arrive_cluster(uint32_t bar, uint32_t cta) {
    asm volatile("{\n.reg .b32 ra;\n"
                 "mapa.shared::cluster.u32 ra, %0, %1;\n"
                 "mbarrier.arrive.release.cluster.shared::cluster.b64 _, [ra];\n}\n"
                 :: "r"(bar), "r"(cta) : "memory");
}
__shared__ volatile uint32_t s_abort;
DEVINL bool mbar_try_wait(uint32_t bar, uint32_t parity) {
    uint32_t ok;
    asm volatile("{\n.reg .pred p;\n"
                 "mbarrier.try_wait.parity.shared::cta.b64 p, [%1], %2;\n"
                 "selp.u32 %0, 1, 0, p;\n}\n"
                 : "=r"(ok) : "r"(bar), "r"(parity) : "memory");
    return ok != 0;
}
DEVINL void mbar_wait(uint32_t bar, uint32_t parity) {
    if (mbar_try_wait(bar, parity)) return;
    uint32_t n = 0;
    while (!mbar_try_wait(bar, parity)) {
        if ((++n & 1023u) == 0 && (n > (1u << 21) || s_abort)) { s_abort = 1; return; }
    }
}
DEVINL bool mbar_try_wait_cl(uint32_t bar, uint32_t parity) {
    uint32_t ok;
    asm volatile("{\n.reg .pred p;\n"
                 "mbarrier.try_wait.parity.acquire.cluster.shared::cta.b64 p, [%1], %2;\n"
                 "selp.u32 %0, 1, 0, p;\n}\n"
                 : "=r"(ok) : "r"(bar), "r"(parity) : "memory");
    return ok != 0;
}
DEVINL void mbar_wait_cl(uint32_t bar, uint32_t parity) {
    if (mbar_try_wait_cl(bar, parity)) return;
    uint32_t n = 0;
    while (!mbar_try_wait_cl(bar, parity)) {
        if ((++n & 1023u) == 0 && (n > (1u << 21) || s_abort)) { s_abort = 1; return; }
    }
}

DEVINL void tma_load_2d(uint32_t dst, const CUtensorMap* tm, int c0, int c1, uint32_t bar) {
    asm volatile("cp.async.bulk.tensor.2d.shared::cluster.global.mbarrier::complete_tx::bytes [%0], [%1, {%3, %4}], [%2];"
                 :: "r"(dst), "l"(tm), "r"(bar), "r"(c0), "r"(c1) : "memory");
}
DEVINL void tma_load_2d_mc(uint32_t dst, const CUtensorMap* tm, int c0, int c1, uint32_t bar, uint16_t mask) {
    asm volatile("cp.async.bulk.tensor.2d.shared::cluster.global.mbarrier::complete_tx::bytes.multicast::cluster [%0], [%1, {%3, %4}], [%2], %5;"
                 :: "r"(dst), "l"(tm), "r"(bar), "r"(c0), "r"(c1), "h"(mask) : "memory");
}
DEVINL void prefetch_tmap(const CUtensorMap* tm) {
    asm volatile("prefetch.tensormap [%0];" :: "l"(tm) : "memory");
}

DEVINL void wg_fence() { asm volatile("wgmma.fence.sync.aligned;" ::: "memory"); }
DEVINL void wg_commit() { asm volatile("wgmma.commit_group.sync.aligned;" ::: "memory"); }
template <int N> DEVINL void wg_wait() { asm volatile("wgmma.wait_group.sync.aligned %0;" :: "n"(N) : "memory"); }

DEVINL void named_sync(int id, int n) { asm volatile("bar.sync %0, %1;" :: "r"(id), "r"(n) : "memory"); }
DEVINL void named_arrive(int id, int n) { asm volatile("bar.arrive %0, %1;" :: "r"(id), "r"(n) : "memory"); }

DEVINL void cluster_sync_all() {
    asm volatile("barrier.cluster.arrive.release.aligned;\nbarrier.cluster.wait.acquire.aligned;" ::: "memory");
}
DEVINL uint32_t cluster_ctarank() { uint32_t r; asm volatile("mov.u32 %0, %%cluster_ctarank;" : "=r"(r)); return r; }

DEVINL float ex2(float x) { float y; asm("ex2.approx.ftz.f32 %0, %1;" : "=f"(y) : "f"(x)); return y; }
DEVINL uint32_t pack_bf16(float lo, float hi) {
    uint32_t r; asm("cvt.rn.bf16x2.f32 %0, %1, %2;" : "=r"(r) : "f"(hi), "f"(lo)); return r;
}
DEVINL float bf16_round(float x) { return __bfloat162float(__float2bfloat16_rn(x)); }
DEVINL float silu_f(float x) { return __fdividef(x, 1.0f + __expf(-x)); }

DEVINL uint64_t make_desc(uint32_t addr, uint32_t lbo_bytes, uint32_t sbo_bytes) {
    uint64_t d = 0;
    d |= (uint64_t)((addr & 0x3FFFF) >> 4);
    d |= (uint64_t)((lbo_bytes >> 4) & 0x3FFF) << 16;
    d |= (uint64_t)((sbo_bytes >> 4) & 0x3FFF) << 32;
    d |= (uint64_t)1 << 62;
    return d;
}

#define ACC64(d) \
    "+f"(d[0]), "+f"(d[1]), "+f"(d[2]), "+f"(d[3]), "+f"(d[4]), "+f"(d[5]), "+f"(d[6]), "+f"(d[7]), \
    "+f"(d[8]), "+f"(d[9]), "+f"(d[10]), "+f"(d[11]), "+f"(d[12]), "+f"(d[13]), "+f"(d[14]), "+f"(d[15]), \
    "+f"(d[16]), "+f"(d[17]), "+f"(d[18]), "+f"(d[19]), "+f"(d[20]), "+f"(d[21]), "+f"(d[22]), "+f"(d[23]), \
    "+f"(d[24]), "+f"(d[25]), "+f"(d[26]), "+f"(d[27]), "+f"(d[28]), "+f"(d[29]), "+f"(d[30]), "+f"(d[31]), \
    "+f"(d[32]), "+f"(d[33]), "+f"(d[34]), "+f"(d[35]), "+f"(d[36]), "+f"(d[37]), "+f"(d[38]), "+f"(d[39]), \
    "+f"(d[40]), "+f"(d[41]), "+f"(d[42]), "+f"(d[43]), "+f"(d[44]), "+f"(d[45]), "+f"(d[46]), "+f"(d[47]), \
    "+f"(d[48]), "+f"(d[49]), "+f"(d[50]), "+f"(d[51]), "+f"(d[52]), "+f"(d[53]), "+f"(d[54]), "+f"(d[55]), \
    "+f"(d[56]), "+f"(d[57]), "+f"(d[58]), "+f"(d[59]), "+f"(d[60]), "+f"(d[61]), "+f"(d[62]), "+f"(d[63])

#define ACC64_STR \
    "{%0, %1, %2, %3, %4, %5, %6, %7, %8, %9, %10, %11, %12, %13, %14, %15, " \
    "%16, %17, %18, %19, %20, %21, %22, %23, %24, %25, %26, %27, %28, %29, %30, %31, " \
    "%32, %33, %34, %35, %36, %37, %38, %39, %40, %41, %42, %43, %44, %45, %46, %47, " \
    "%48, %49, %50, %51, %52, %53, %54, %55, %56, %57, %58, %59, %60, %61, %62, %63}"

template <int TB>
DEVINL void wgmma_ss(float (&d)[64], uint64_t da, uint64_t db, int scale_d) {
    asm volatile("{\n.reg .pred p;\nsetp.ne.b32 p, %66, 0;\n"
                 "wgmma.mma_async.sync.aligned.m64n128k16.f32.bf16.bf16 " ACC64_STR ", %64, %65, p, 1, 1, 0, %67;\n}\n"
                 : ACC64(d) : "l"(da), "l"(db), "r"(scale_d), "n"(TB));
}
template <int TB>
DEVINL void wgmma_rs(float (&d)[64], uint32_t a0, uint32_t a1, uint32_t a2, uint32_t a3, uint64_t db, int scale_d) {
    asm volatile("{\n.reg .pred p;\nsetp.ne.b32 p, %69, 0;\n"
                 "wgmma.mma_async.sync.aligned.m64n128k16.f32.bf16.bf16 " ACC64_STR ", {%64, %65, %66, %67}, %68, p, 1, 1, %70;\n}\n"
                 : ACC64(d) : "r"(a0), "r"(a1), "r"(a2), "r"(a3), "l"(db), "r"(scale_d), "n"(TB));
}

DEVINL void fence_regs(float (&d)[64]) {
#pragma unroll
    for (int i = 0; i < 64; i++) asm volatile("" : "+f"(d[i]) :: "memory");
}
DEVINL void fence_regs_u(uint32_t (&d)[32]) {
#pragma unroll
    for (int i = 0; i < 32; i++) asm volatile("" : "+r"(d[i]) :: "memory");
}

__global__ void __launch_bounds__(256) ln_kernel(const __nv_bfloat16* __restrict__ x) {
    asm volatile("griddepcontrol.launch_dependents;");
    const int warp = threadIdx.x >> 5, lane = threadIdx.x & 31;
    const int row = blockIdx.x * 8 + warp;
    {
        float4 z = make_float4(0.f, 0.f, 0.f, 0.f);
        float4* a = reinterpret_cast<float4*>(g_sacc) + (size_t)blockIdx.x * 1024;
        float4* b = reinterpret_cast<float4*>(g_facc) + (size_t)blockIdx.x * 1024;
#pragma unroll
        for (int i = 0; i < 4; i++) { a[i * 256 + threadIdx.x] = z; b[i * 256 + threadIdx.x] = z; }
    }
    const uint4* xr = reinterpret_cast<const uint4*>(x + (size_t)row * DM);
    uint4 v[2];
    v[0] = xr[lane]; v[1] = xr[lane + 32];
    float f[16];
#pragma unroll
    for (int i = 0; i < 2; i++) {
        const __nv_bfloat162* h = reinterpret_cast<const __nv_bfloat162*>(&v[i]);
#pragma unroll
        for (int j = 0; j < 4; j++) { float2 t = __bfloat1622float2(h[j]); f[i * 8 + 2 * j] = t.x; f[i * 8 + 2 * j + 1] = t.y; }
    }
    float s = 0.f;
#pragma unroll
    for (int i = 0; i < 16; i++) s += f[i];
#pragma unroll
    for (int o = 16; o > 0; o >>= 1) s += __shfl_xor_sync(0xffffffffu, s, o);
    const float mean = s * (1.0f / DM);
    float q = 0.f;
#pragma unroll
    for (int i = 0; i < 16; i++) { float d = f[i] - mean; q += d * d; }
#pragma unroll
    for (int o = 16; o > 0; o >>= 1) q += __shfl_xor_sync(0xffffffffu, q, o);
    const float mb = bf16_round(mean);
    const float vb = bf16_round(q * (1.0f / DM));
    const float den = bf16_round(sqrtf(bf16_round(vb + 1e-5f)));
    uint4 o4[2];
#pragma unroll
    for (int i = 0; i < 2; i++) {
        uint32_t* w = reinterpret_cast<uint32_t*>(&o4[i]);
#pragma unroll
        for (int j = 0; j < 4; j++) {
            float a = bf16_round(f[i * 8 + 2 * j] - mb) / den;
            float b = bf16_round(f[i * 8 + 2 * j + 1] - mb) / den;
            w[j] = pack_bf16(a, b);
        }
    }
    uint4* orow = reinterpret_cast<uint4*>(g_xn + (size_t)row * DM);
    orow[lane] = o4[0]; orow[lane + 32] = o4[1];
}

__global__ void __launch_bounds__(256) final_kernel(const __nv_bfloat16* __restrict__ x, __nv_bfloat16* __restrict__ out) {
    const int i = (blockIdx.x * 256 + threadIdx.x) * 8;
    uint4 xv = *reinterpret_cast<const uint4*>(x + i);
    asm volatile("griddepcontrol.wait;" ::: "memory");
    float sv[8], fv[8];
    *reinterpret_cast<float4*>(&sv[0]) = __ldcg(reinterpret_cast<const float4*>(g_sacc + i));
    *reinterpret_cast<float4*>(&sv[4]) = __ldcg(reinterpret_cast<const float4*>(g_sacc + i + 4));
    *reinterpret_cast<float4*>(&fv[0]) = __ldcg(reinterpret_cast<const float4*>(g_facc + i));
    *reinterpret_cast<float4*>(&fv[4]) = __ldcg(reinterpret_cast<const float4*>(g_facc + i + 4));
    const __nv_bfloat162* xh = reinterpret_cast<const __nv_bfloat162*>(&xv);
    uint4 ov; uint32_t* ow = reinterpret_cast<uint32_t*>(&ov);
#pragma unroll
    for (int j = 0; j < 4; j++) {
        float2 xf = __bfloat1622float2(xh[j]);
        float r[2];
#pragma unroll
        for (int t = 0; t < 2; t++) {
            float s = bf16_round(sv[2 * j + t]);
            float fo = bf16_round(fv[2 * j + t]);
            float g = bf16_round(fo / (1.0f + __expf(-fo)));
            float sg = bf16_round(s * g);
            r[t] = (t ? xf.y : xf.x) + sg;
        }
        ow[j] = pack_bf16(r[0], r[1]);
    }
    *reinterpret_cast<uint4*>(out + i) = ov;
}

struct Unit { int is_attn; int idx; int qpair; };
DEVINL int num_units(int cl) { return cl < 64 ? 5 : 24; }
DEVINL Unit get_unit(int cl, int i) {
    Unit u;
    if (cl < 64) {
        if (i < 4) { int p = cl + 64 * i; u.is_attn = 1; u.idx = p >> 3; u.qpair = p & 7; }
        else       { int f = cl;          u.is_attn = 0; u.idx = f >> 3; u.qpair = f & 7; }
    } else {
        int f = 64 + (cl - 64) * 24 + i;  u.is_attn = 0; u.idx = f >> 3; u.qpair = f & 7;
    }
    return u;
}

struct __align__(64) Params {
    CUtensorMap xn, wq, w1, k, v, wo, w2;
};

__global__ void __cluster_dims__(CLUSTER, 1, 1) __launch_bounds__(NTHREADS, 1)
mega_kernel(const __grid_constant__ Params prm) {
    extern __shared__ uint8_t smem_raw[];
    const uint32_t smem_base = (smem_u32(smem_raw) + 1023u) & ~1023u;
    const uint32_t bar_base = smem_base + NSLOT * SLOT_BYTES;
    auto full_bar = [&](uint32_t s) { return bar_base + s * 8; };
    auto empty_bar = [&](uint32_t s) { return bar_base + (NSLOT + s) * 8; };

    const int tid = threadIdx.x;
    const int wg = tid >> 7;
    const uint32_t rank = cluster_ctarank();
    const int cl = blockIdx.x / CLUSTER;

    if (tid == 0) {
        s_abort = 0;
        for (int s = 0; s < NSLOT; s++) { mbar_init(full_bar(s), 1); mbar_init(empty_bar(s), 8 * CLUSTER); }
        asm volatile("fence.mbarrier_init.release.cluster;" ::: "memory");
    }
    __syncthreads();
    cluster_sync_all();

    const int nunits = num_units(cl);

    if (wg == 0) {
        asm volatile("setmaxnreg.dec.sync.aligned.u32 24;");
        if (tid == 0) {
            prefetch_tmap(&prm.xn); prefetch_tmap(&prm.wq); prefetch_tmap(&prm.w1); prefetch_tmap(&prm.k);
            prefetch_tmap(&prm.v); prefetch_tmap(&prm.wo); prefetch_tmap(&prm.w2);
            asm volatile("griddepcontrol.wait;" ::: "memory");
            uint32_t slot = 0, phase = 0;
            auto acquire = [&]() -> uint32_t {
                mbar_wait_cl(empty_bar(slot), phase ^ 1);
                mbar_expect_tx(full_bar(slot), SLOT_BYTES);
                return smem_base + slot * SLOT_BYTES;
            };
            auto advance = [&]() { if (++slot == NSLOT) { slot = 0; phase ^= 1; } };
            auto load_tile128 = [&](const CUtensorMap* tm, int row0, int col0) {
                uint32_t dst = acquire();
                uint32_t fb = full_bar(slot);
                tma_load_2d_mc(dst + rank * 8192, tm, col0, row0 + rank * 64, fb, (uint16_t)3);
                tma_load_2d_mc(dst + 16384 + rank * 8192, tm, col0 + 64, row0 + rank * 64, fb, (uint16_t)3);
                advance();
            };
            for (int ui = 0; ui < nunits; ui++) {
                const Unit u = get_unit(cl, ui);
                const int qt = u.qpair * 2 + rank;
                const CUtensorMap* tin = u.is_attn ? &prm.wq : &prm.w1;
                const CUtensorMap* tout = u.is_attn ? &prm.wo : &prm.w2;
                for (int c = 0; c < 8; c++) {
                    uint32_t dst = acquire();
                    uint32_t fb = full_bar(slot);
                    tma_load_2d(dst, &prm.xn, c * 64, qt * 128, fb);
                    tma_load_2d_mc(dst + 16384 + rank * 8192, tin, u.idx * 128 + rank * 64, c * 64, fb, (uint16_t)3);
                    advance();
                }
                if (u.is_attn) {
                    const int r0 = u.idx * SEQ;
                    load_tile128(&prm.k, r0, 0);
                    for (int n = 1; n < 16; n++) {
                        load_tile128(&prm.k, r0 + n * 128, 0);
                        load_tile128(&prm.v, r0 + (n - 1) * 128, 0);
                    }
                    load_tile128(&prm.v, r0 + 15 * 128, 0);
                }
                for (int c = 0; c < 4; c++) load_tile128(tout, u.idx * 128, c * 128);
            }
        }
        __syncwarp();
        cluster_sync_all();
    } else {
        asm volatile("setmaxnreg.inc.sync.aligned.u32 240;");
        const int w = wg - 1;
        const int lane = tid & 31;
        const int wq = (tid >> 5) & 3;
        const int BAR_SELF = 1 + w, BAR_OTHER = 1 + (w ^ 1);

        uint32_t slot = 0, phase = 0;
        auto advance = [&]() { if (++slot == NSLOT) { slot = 0; phase ^= 1; } };
        auto release = [&](uint32_t s) {
            if (lane == 0) { mbar_arrive_cluster(empty_bar(s), 0); mbar_arrive_cluster(empty_bar(s), 1); }
        };

        float O[64], S[64];
        uint32_t A[32], P[32];
        const float cexp = 0.08838834764831845f * 1.4426950408889634f;

        if (w == 1) named_arrive(1, 256);

        for (int ui = 0; ui < nunits; ui++) {
            const Unit u = get_unit(cl, ui);
            const int qt = u.qpair * 2 + rank;
            {
                uint32_t prev = 0;
#pragma unroll 1
                for (int c = 0; c < 8; c++) {
                    mbar_wait(full_bar(slot), phase);
                    const uint32_t base = smem_base + slot * SLOT_BYTES;
                    const uint64_t da = make_desc(base + w * 8192, 16, 1024);
                    const uint64_t db = make_desc(base + 16384, 8192, 1024);
                    wg_fence();
#pragma unroll
                    for (int kk = 0; kk < 4; kk++)
                        wgmma_ss<1>(S, da + kk * 2, db + kk * 128, (c | kk) != 0);
                    wg_commit();
                    if (c > 0) { wg_wait<1>(); release(prev); }
                    prev = slot;
                    advance();
                }
                wg_wait<0>();
                fence_regs(S);
                release(prev);
            }
            if (u.is_attn) {
#pragma unroll
                for (int i = 0; i < 32; i++) A[i] = pack_bf16(S[2 * i], S[2 * i + 1]);
                float m0 = -INFINITY, m1 = -INFINITY, l0 = 0.f, l1 = 0.f;
                auto issue_qk = [&]() {
                    const uint32_t base = smem_base + slot * SLOT_BYTES;
                    const uint64_t db = make_desc(base, 16, 1024);
#pragma unroll
                    for (int kk = 0; kk < 8; kk++)
                        wgmma_rs<0>(S, A[4 * kk], A[4 * kk + 1], A[4 * kk + 2], A[4 * kk + 3],
                                    db + (kk >> 2) * 1024 + (kk & 3) * 2, kk != 0);
                    wg_commit();
                };
                auto issue_pv = [&](int first) {
                    const uint32_t base = smem_base + slot * SLOT_BYTES;
                    const uint64_t db = make_desc(base, 16384, 1024);
#pragma unroll
                    for (int kk = 0; kk < 8; kk++)
                        wgmma_rs<1>(O, P[4 * kk], P[4 * kk + 1], P[4 * kk + 2], P[4 * kk + 3],
                                    db + kk * 128, (kk != 0) || !first);
                    wg_commit();
                };
                float sc0, sc1;
                auto softmax = [&]() {
                    float a0 = fmaxf(S[0], S[1]), a1 = fmaxf(S[2], S[3]);
#pragma unroll
                    for (int j = 1; j < 16; j++) {
                        a0 = fmaxf(a0, fmaxf(S[4 * j], S[4 * j + 1]));
                        a1 = fmaxf(a1, fmaxf(S[4 * j + 2], S[4 * j + 3]));
                    }
                    a0 = fmaxf(a0, __shfl_xor_sync(0xffffffffu, a0, 1));
                    a1 = fmaxf(a1, __shfl_xor_sync(0xffffffffu, a1, 1));
                    a0 = fmaxf(a0, __shfl_xor_sync(0xffffffffu, a0, 2));
                    a1 = fmaxf(a1, __shfl_xor_sync(0xffffffffu, a1, 2));
                    const float n0 = fmaxf(m0, a0), n1 = fmaxf(m1, a1);
                    sc0 = ex2((m0 - n0) * cexp); sc1 = ex2((m1 - n1) * cexp);
                    m0 = n0; m1 = n1;
                    const float b0 = -n0 * cexp, b1 = -n1 * cexp;
                    float s0 = 0.f, s1 = 0.f;
#pragma unroll
                    for (int j = 0; j < 16; j++) {
                        S[4 * j]     = ex2(fmaf(S[4 * j], cexp, b0));
                        S[4 * j + 1] = ex2(fmaf(S[4 * j + 1], cexp, b0));
                        S[4 * j + 2] = ex2(fmaf(S[4 * j + 2], cexp, b1));
                        S[4 * j + 3] = ex2(fmaf(S[4 * j + 3], cexp, b1));
                        s0 += S[4 * j] + S[4 * j + 1];
                        s1 += S[4 * j + 2] + S[4 * j + 3];
                    }
                    l0 = l0 * sc0 + s0; l1 = l1 * sc1 + s1;
                };
                auto make_p = [&]() {
#pragma unroll
                    for (int i = 0; i < 32; i++) P[i] = pack_bf16(S[2 * i], S[2 * i + 1]);
                };

                mbar_wait(full_bar(slot), phase);
                named_sync(BAR_SELF, 256);
                wg_fence();
                issue_qk();
                named_arrive(BAR_OTHER, 256);
                wg_wait<0>();
                fence_regs(S);
                release(slot); advance();
                softmax();
                make_p();
#pragma unroll 1
                for (int n = 1; n < 16; n++) {
                    const uint32_t ks = slot;
                    mbar_wait(full_bar(slot), phase);
                    named_sync(BAR_SELF, 256);
                    wg_fence();
                    issue_qk();
                    advance();
                    const uint32_t vs = slot;
                    mbar_wait(full_bar(slot), phase);
                    issue_pv(n == 1);
                    advance();
                    named_arrive(BAR_OTHER, 256);
                    wg_wait<1>();
                    fence_regs(S);
                    release(ks);
                    softmax();
                    wg_wait<0>();
                    fence_regs(O);
                    fence_regs_u(P);
                    release(vs);
#pragma unroll
                    for (int j = 0; j < 16; j++) {
                        O[4 * j] *= sc0; O[4 * j + 1] *= sc0; O[4 * j + 2] *= sc1; O[4 * j + 3] *= sc1;
                    }
                    make_p();
                }
                mbar_wait(full_bar(slot), phase);
                wg_fence();
                issue_pv(0);
                wg_wait<0>();
                fence_regs(O);
                release(slot); advance();
                l0 += __shfl_xor_sync(0xffffffffu, l0, 1); l1 += __shfl_xor_sync(0xffffffffu, l1, 1);
                l0 += __shfl_xor_sync(0xffffffffu, l0, 2); l1 += __shfl_xor_sync(0xffffffffu, l1, 2);
                const float i0 = 1.0f / l0, i1 = 1.0f / l1;
#pragma unroll
                for (int j = 0; j < 16; j++) {
                    A[2 * j]     = pack_bf16(O[4 * j] * i0, O[4 * j + 1] * i0);
                    A[2 * j + 1] = pack_bf16(O[4 * j + 2] * i1, O[4 * j + 3] * i1);
                }
            } else {
#pragma unroll
                for (int i = 0; i < 32; i++)
                    A[i] = pack_bf16(silu_f(bf16_round(S[2 * i])), silu_f(bf16_round(S[2 * i + 1])));
            }
            {
                float* gacc = (u.is_attn ? g_sacc : g_facc) + (size_t)(qt * 128 + w * 64 + wq * 16 + (lane >> 2)) * DM + (lane & 3) * 2;
                auto issue_out = [&](float (&D)[64]) {
                    mbar_wait(full_bar(slot), phase);
                    const uint32_t base = smem_base + slot * SLOT_BYTES;
                    const uint64_t db = make_desc(base, 16384, 1024);
                    wg_fence();
#pragma unroll
                    for (int kk = 0; kk < 8; kk++)
                        wgmma_rs<1>(D, A[4 * kk], A[4 * kk + 1], A[4 * kk + 2], A[4 * kk + 3], db + kk * 128, kk != 0);
                    wg_commit();
                };
                auto store_out = [&](float (&D)[64], int c) {
                    float* p = gacc + c * 128;
#pragma unroll
                    for (int j = 0; j < 16; j++) {
                        asm volatile("red.global.add.v2.f32 [%0], {%1, %2};" :: "l"(p + j * 8), "f"(D[4 * j]), "f"(D[4 * j + 1]) : "memory");
                        asm volatile("red.global.add.v2.f32 [%0], {%1, %2};" :: "l"(p + j * 8 + 8 * DM), "f"(D[4 * j + 2]), "f"(D[4 * j + 3]) : "memory");
                    }
                };
                uint32_t s0 = slot; issue_out(S); advance();
                uint32_t s1 = slot; issue_out(O); advance();
                wg_wait<1>(); fence_regs(S); release(s0); store_out(S, 0);
                s0 = slot; issue_out(S); advance();
                wg_wait<1>(); fence_regs(O); release(s1); store_out(O, 1);
                s1 = slot; issue_out(O); advance();
                wg_wait<1>(); fence_regs(S); release(s0); store_out(S, 2);
                wg_wait<0>(); fence_regs(O); release(s1); store_out(O, 3);
            }
        }
        asm volatile("griddepcontrol.launch_dependents;");
        cluster_sync_all();
    }
}

typedef CUresult (*PFN_encodeTiled)(CUtensorMap*, CUtensorMapDataType, cuuint32_t, void*, const cuuint64_t*,
                                    const cuuint64_t*, const cuuint32_t*, const cuuint32_t*, CUtensorMapInterleave,
                                    CUtensorMapSwizzle, CUtensorMapL2promotion, CUtensorMapFloatOOBfill);

static void make_tmap(PFN_encodeTiled enc, CUtensorMap* tm, const void* ptr, uint64_t rows, uint64_t cols,
                      uint32_t box_rows, uint32_t box_cols) {
    cuuint64_t gdim[2] = {cols, rows};
    cuuint64_t gstr[1] = {cols * 2};
    cuuint32_t box[2] = {box_cols, box_rows};
    cuuint32_t estr[2] = {1, 1};
    enc(tm, CU_TENSOR_MAP_DATA_TYPE_BFLOAT16, 2, const_cast<void*>(ptr), gdim, gstr, box, estr,
        CU_TENSOR_MAP_INTERLEAVE_NONE, CU_TENSOR_MAP_SWIZZLE_128B, CU_TENSOR_MAP_L2_PROMOTION_L2_256B,
        CU_TENSOR_MAP_FLOAT_OOB_FILL_NONE);
}

extern "C" void kernel_launch(void* const* d_in, const int* in_sizes, int n_in, void* d_out, int out_size) {
    const __nv_bfloat16* x  = (const __nv_bfloat16*)d_in[0];
    const void* kc = d_in[1];
    const void* vc = d_in[2];
    const void* wq = d_in[3];
    const void* wo = d_in[4];
    const void* w1 = d_in[6];
    const void* w2 = d_in[7];
    __nv_bfloat16* out = (__nv_bfloat16*)d_out;

    static PFN_encodeTiled enc = nullptr;
    static void* xn_ptr = nullptr;
    if (!enc) {
        void* fn = nullptr;
        cudaDriverEntryPointQueryResult qres;
        cudaGetDriverEntryPoint("cuTensorMapEncodeTiled", &fn, cudaEnableDefault, &qres);
        enc = (PFN_encodeTiled)fn;
        cudaGetSymbolAddress(&xn_ptr, g_xn);
        cudaFuncSetAttribute(mega_kernel, cudaFuncAttributeMaxDynamicSharedMemorySize, SMEM_BYTES);
    }
    Params prm;
    make_tmap(enc, &prm.xn, xn_ptr, SEQ, DM, 128, 64);
    make_tmap(enc, &prm.wq, wq, DM, NH * DH, 64, 64);
    make_tmap(enc, &prm.w1, w1, DM, FF, 64, 64);
    make_tmap(enc, &prm.k, kc, (uint64_t)NH * SEQ, DH, 64, 64);
    make_tmap(enc, &prm.v, vc, (uint64_t)NH * SEQ, DH, 64, 64);
    make_tmap(enc, &prm.wo, wo, NH * DH, DM, 64, 64);
    make_tmap(enc, &prm.w2, w2, FF, DM, 64, 64);

    cudaStream_t st = cudaStreamPerThread;
    ln_kernel<<<SEQ / 8, 256, 0, st>>>(x);

    cudaLaunchAttribute attr[1];
    attr[0].id = cudaLaunchAttributeProgrammaticStreamSerialization;
    attr[0].val.programmaticStreamSerializationAllowed = 1;
    {
        cudaLaunchConfig_t cfg = {};
        cfg.gridDim = dim3(132); cfg.blockDim = dim3(NTHREADS); cfg.dynamicSmemBytes = SMEM_BYTES; cfg.stream = st;
        cfg.attrs = attr; cfg.numAttrs = 1;
        cudaLaunchKernelEx(&cfg, mega_kernel, prm);
    }
    {
        cudaLaunchConfig_t cfg = {};
        cfg.gridDim = dim3(SEQ * DM / (256 * 8)); cfg.blockDim = dim3(256); cfg.dynamicSmemBytes = 0; cfg.stream = st;
        cfg.attrs = attr; cfg.numAttrs = 1;
        cudaLaunchKernelEx(&cfg, final_kernel, x, out);
    }
}
```

```cpp
#define KTOK 0
#define ESPLIT 14
#define TOKV (s0 + s1)
#define KP 6
#define PF 0
#define PSLEEP 400
#define CLD 27
#include <cuda_runtime.h>
#include <cuda_bf16.h>
#include <cuda.h>
#include <stdint.h>
#include <type_traits>

#define DEVINL __device__ __forceinline__

constexpr int SEQ = 2048, DM = 512, NH = 32, DH = 128, FF = 1792;
constexpr int CLUSTER = 2;
constexpr int NSLOT = 4;
constexpr int NSTASH = 3;
constexpr int MAXSLOT = 6;
constexpr int SLOT_BYTES = 32768;
constexpr int NTHREADS = 384;
constexpr int SMEM_BYTES = (NSLOT + NSTASH) * SLOT_BYTES + 1024   + 256  ;

__device__ __nv_bfloat16 g_xn[SEQ * DM];
__device__ float g_sacc[SEQ * DM];
__device__ __nv_bfloat16 g_h[SEQ * FF];
__device__ unsigned int g_cnt[16];
__device__ float4 g_part[32 * 2 * 2 * 16 * 128];
__device__ unsigned int g_pflag[128];
__device__ unsigned int g_done[16 * 32];
#define TS() do { } while (0)
#define GT_MIN(i) do { } while (0)
#define GT_MAX(i) do { } while (0)

DEVINL uint32_t smem_u32(const void* p) { return (uint32_t)__cvta_generic_to_shared(p); }

DEVINL void mbar_init(uint32_t bar, uint32_t count) {
    asm volatile("mbarrier.init.shared::cta.b64 [%0], %1;" :: "r"(bar), "r"(count) : "memory");
}
DEVINL void mbar_expect_tx(uint32_t bar, uint32_t bytes) {
    asm volatile("mbarrier.arrive.expect_tx.shared::cta.b64 _, [%0], %1;" :: "r"(bar), "r"(bytes) : "memory");
}
DEVINL void mbar_arrive(uint32_t bar) {
    asm volatile("mbarrier.arrive.shared::cta.b64 _, [%0];" :: "r"(bar) : "memory");
}
DEVINL void mbar_arrive_cluster_n(uint32_t bar, uint32_t cta, uint32_t n) {
    asm volatile("{\n.reg .b32 ra;\n"
                 "mapa.shared::cluster.u32 ra, %0, %1;\n"
                 "mbarrier.arrive.shared::cluster.b64 _, [ra], %2;\n}\n"
                 :: "r"(bar), "r"(cta), "r"(n) : "memory");
}
DEVINL void mbar_arrive_cluster(uint32_t bar, uint32_t cta) {
    asm volatile("{\n.reg .b32 ra;\n"
                 "mapa.shared::cluster.u32 ra, %0, %1;\n"
                 "mbarrier.arrive.shared::cluster.b64 _, [ra];\n}\n"
                 :: "r"(bar), "r"(cta) : "memory");
}
__shared__ volatile uint32_t s_limit;
DEVINL bool mbar_try_wait(uint32_t bar, uint32_t parity) {
    uint32_t ok;
    asm volatile("{\n.reg .pred p;\n"
                 "mbarrier.try_wait.parity.shared::cta.b64 p, [%1], %2;\n"
                 "selp.u32 %0, 1, 0, p;\n}\n"
                 : "=r"(ok) : "r"(bar), "r"(parity) : "memory");
    return ok != 0;
}
DEVINL void mbar_wait(uint32_t bar, uint32_t parity) {
    uint32_t n = 0;
    while (!mbar_try_wait(bar, parity)) {
        if (++n > s_limit) { s_limit = 0; break; }
    }
}

DEVINL void tma_load_2d(uint32_t dst, const CUtensorMap* tm, int c0, int c1, uint32_t bar) {
    asm volatile("cp.async.bulk.tensor.2d.shared::cluster.global.mbarrier::complete_tx::bytes [%0], [%1, {%3, %4}], [%2];"
                 :: "r"(dst), "l"(tm), "r"(bar), "r"(c0), "r"(c1) : "memory");
}
DEVINL void tma_load_2d_mc(uint32_t dst, const CUtensorMap* tm, int c0, int c1, uint32_t bar, uint16_t mask) {
    asm volatile("cp.async.bulk.tensor.2d.shared::cluster.global.mbarrier::complete_tx::bytes.multicast::cluster [%0], [%1, {%3, %4}], [%2], %5;"
                 :: "r"(dst), "l"(tm), "r"(bar), "r"(c0), "r"(c1), "h"(mask) : "memory");
}
DEVINL void tma_store_2d(const CUtensorMap* tm, int c0, int c1, uint32_t src) {
    asm volatile("cp.async.bulk.tensor.2d.global.shared::cta.bulk_group [%0, {%2, %3}], [%1];"
                 :: "l"(tm), "r"(src), "r"(c0), "r"(c1) : "memory");
}
DEVINL void tma_red_add_2d(const CUtensorMap* tm, int c0, int c1, uint32_t src) {
    asm volatile("cp.reduce.async.bulk.tensor.2d.global.shared::cta.add.tile.bulk_group [%0, {%2, %3}], [%1];"
                 :: "l"(tm), "r"(src), "r"(c0), "r"(c1) : "memory");
}
DEVINL void tma_prefetch_2d(const CUtensorMap* tm, int c0, int c1) {
    asm volatile("cp.async.bulk.prefetch.tensor.2d.L2.global.tile [%0, {%1, %2}];" :: "l"(tm), "r"(c0), "r"(c1) : "memory");
}
DEVINL void prefetch_tmap(const CUtensorMap* tm) {
    asm volatile("prefetch.tensormap [%0];" :: "l"(tm) : "memory");
}

DEVINL void wg_fence() { asm volatile("wgmma.fence.sync.aligned;" ::: "memory"); }
DEVINL void wg_commit() { asm volatile("wgmma.commit_group.sync.aligned;" ::: "memory"); }
template <int N> DEVINL void wg_wait() { asm volatile("wgmma.wait_group.sync.aligned %0;" :: "n"(N) : "memory"); }

DEVINL void named_sync(int id, int n) { asm volatile("bar.sync %0, %1;" :: "r"(id), "r"(n) : "memory"); }
DEVINL void named_sync_if(bool c, int id, int n) {
    asm volatile("{\n.reg .pred p;\nsetp.ne.b32 p, %0, 0;\n@p bar.sync %1, %2;\n}\n" :: "r"((int)c), "r"(id), "r"(n) : "memory");
}
DEVINL void named_arrive(int id, int n) { asm volatile("bar.arrive %0, %1;" :: "r"(id), "r"(n) : "memory"); }

DEVINL void cluster_sync_all() {
    asm volatile("barrier.cluster.arrive.release.aligned;\nbarrier.cluster.wait.acquire.aligned;" ::: "memory");
}
DEVINL uint32_t cluster_ctarank() { uint32_t r; asm volatile("mov.u32 %0, %%cluster_ctarank;" : "=r"(r)); return r; }

DEVINL float ex2(float x) { float y; asm("ex2.approx.ftz.f32 %0, %1;" : "=f"(y) : "f"(x)); return y; }
DEVINL uint32_t pack_bf16(float lo, float hi) {
    uint32_t r; asm("cvt.rn.bf16x2.f32 %0, %1, %2;" : "=r"(r) : "f"(hi), "f"(lo)); return r;
}
DEVINL float bf16_round(float x) { return __bfloat162float(__float2bfloat16_rn(x)); }
DEVINL float rcp_f(float x) { float y; asm("rcp.approx.ftz.f32 %0, %1;" : "=f"(y) : "f"(x)); return y; }
DEVINL float silu_f(float x) { return x * rcp_f(1.0f + ex2(x * -1.4426950408889634f)); }
DEVINL uint32_t silu_packed(uint32_t r) {
    return pack_bf16(silu_f(__uint_as_float(r << 16)), silu_f(__uint_as_float(r & 0xffff0000u)));
}
DEVINL uint32_t silu_pair(float a, float b) { return silu_packed(pack_bf16(a, b)); }

DEVINL uint64_t make_desc(uint32_t addr, uint32_t lbo_bytes, uint32_t sbo_bytes) {
    uint64_t d = 0;
    d |= (uint64_t)((addr & 0x3FFFF) >> 4);
    d |= (uint64_t)((lbo_bytes >> 4) & 0x3FFF) << 16;
    d |= (uint64_t)((sbo_bytes >> 4) & 0x3FFF) << 32;
    d |= (uint64_t)1 << 62;
    return d;
}

#define ACC64(d) \
    "+f"(d[0]), "+f"(d[1]), "+f"(d[2]), "+f"(d[3]), "+f"(d[4]), "+f"(d[5]), "+f"(d[6]), "+f"(d[7]), \
    "+f"(d[8]), "+f"(d[9]), "+f"(d[10]), "+f"(d[11]), "+f"(d[12]), "+f"(d[13]), "+f"(d[14]), "+f"(d[15]), \
    "+f"(d[16]), "+f"(d[17]), "+f"(d[18]), "+f"(d[19]), "+f"(d[20]), "+f"(d[21]), "+f"(d[22]), "+f"(d[23]), \
    "+f"(d[24]), "+f"(d[25]), "+f"(d[26]), "+f"(d[27]), "+f"(d[28]), "+f"(d[29]), "+f"(d[30]), "+f"(d[31]), \
    "+f"(d[32]), "+f"(d[33]), "+f"(d[34]), "+f"(d[35]), "+f"(d[36]), "+f"(d[37]), "+f"(d[38]), "+f"(d[39]), \
    "+f"(d[40]), "+f"(d[41]), "+f"(d[42]), "+f"(d[43]), "+f"(d[44]), "+f"(d[45]), "+f"(d[46]), "+f"(d[47]), \
    "+f"(d[48]), "+f"(d[49]), "+f"(d[50]), "+f"(d[51]), "+f"(d[52]), "+f"(d[53]), "+f"(d[54]), "+f"(d[55]), \
    "+f"(d[56]), "+f"(d[57]), "+f"(d[58]), "+f"(d[59]), "+f"(d[60]), "+f"(d[61]), "+f"(d[62]), "+f"(d[63])

#define ACC64_STR \
    "{%0, %1, %2, %3, %4, %5, %6, %7, %8, %9, %10, %11, %12, %13, %14, %15, " \
    "%16, %17, %18, %19, %20, %21, %22, %23, %24, %25, %26, %27, %28, %29, %30, %31, " \
    "%32, %33, %34, %35, %36, %37, %38, %39, %40, %41, %42, %43, %44, %45, %46, %47, " \
    "%48, %49, %50, %51, %52, %53, %54, %55, %56, %57, %58, %59, %60, %61, %62, %63}"

template <int TB>
DEVINL void wgmma_ss(float (&d)[64], uint64_t da, uint64_t db, int scale_d) {
    asm volatile("{\n.reg .pred p;\nsetp.ne.b32 p, %66, 0;\n"
                 "wgmma.mma_async.sync.aligned.m64n128k16.f32.bf16.bf16 " ACC64_STR ", %64, %65, p, 1, 1, 0, %67;\n}\n"
                 : ACC64(d) : "l"(da), "l"(db), "r"(scale_d), "n"(TB));
}
template <int TB>
DEVINL void wgmma_rs(float (&d)[64], uint32_t a0, uint32_t a1, uint32_t a2, uint32_t a3, uint64_t db, int scale_d) {
    asm volatile("{\n.reg .pred p;\nsetp.ne.b32 p, %69, 0;\n"
                 "wgmma.mma_async.sync.aligned.m64n128k16.f32.bf16.bf16 " ACC64_STR ", {%64, %65, %66, %67}, %68, p, 1, 1, %70;\n}\n"
                 : ACC64(d) : "r"(a0), "r"(a1), "r"(a2), "r"(a3), "l"(db), "r"(scale_d), "n"(TB));
}

template <int H>
DEVINL void wgmma_rs64(float (&d)[64], uint32_t a0, uint32_t a1, uint32_t a2, uint32_t a3, uint64_t db, int scale_d) {
    asm volatile("{\n.reg .pred p;\nsetp.ne.b32 p, %37, 0;\n"
                 "wgmma.mma_async.sync.aligned.m64n64k16.f32.bf16.bf16 "
                 "{%0, %1, %2, %3, %4, %5, %6, %7, %8, %9, %10, %11, %12, %13, %14, %15, "
                 "%16, %17, %18, %19, %20, %21, %22, %23, %24, %25, %26, %27, %28, %29, %30, %31}, "
                 "{%32, %33, %34, %35}, %36, p, 1, 1, 1;\n}\n"
                 : "+f"(d[H * 32 + 0]), "+f"(d[H * 32 + 1]), "+f"(d[H * 32 + 2]), "+f"(d[H * 32 + 3]), "+f"(d[H * 32 + 4]), "+f"(d[H * 32 + 5]),
                   "+f"(d[H * 32 + 6]), "+f"(d[H * 32 + 7]), "+f"(d[H * 32 + 8]), "+f"(d[H * 32 + 9]), "+f"(d[H * 32 + 10]), "+f"(d[H * 32 + 11]),
                   "+f"(d[H * 32 + 12]), "+f"(d[H * 32 + 13]), "+f"(d[H * 32 + 14]), "+f"(d[H * 32 + 15]), "+f"(d[H * 32 + 16]), "+f"(d[H * 32 + 17]),
                   "+f"(d[H * 32 + 18]), "+f"(d[H * 32 + 19]), "+f"(d[H * 32 + 20]), "+f"(d[H * 32 + 21]), "+f"(d[H * 32 + 22]), "+f"(d[H * 32 + 23]),
                   "+f"(d[H * 32 + 24]), "+f"(d[H * 32 + 25]), "+f"(d[H * 32 + 26]), "+f"(d[H * 32 + 27]), "+f"(d[H * 32 + 28]), "+f"(d[H * 32 + 29]),
                   "+f"(d[H * 32 + 30]), "+f"(d[H * 32 + 31])
                 : "r"(a0), "r"(a1), "r"(a2), "r"(a3), "l"(db), "r"(scale_d));
}
template <int H>
DEVINL void fence_half(float (&d)[64]) {
#pragma unroll
    for (int i = 0; i < 32; i++) asm volatile("" : "+f"(d[H * 32 + i]) :: "memory");
}

#define ACC64_STR2 \
    "%64, %65, %66, %67, %68, %69, %70, %71, %72, %73, %74, %75, %76, %77, %78, %79, " \
    "%80, %81, %82, %83, %84, %85, %86, %87, %88, %89, %90, %91, %92, %93, %94, %95, " \
    "%96, %97, %98, %99, %100, %101, %102, %103, %104, %105, %106, %107, %108, %109, %110, %111, " \
    "%112, %113, %114, %115, %116, %117, %118, %119, %120, %121, %122, %123, %124, %125, %126, %127}"
#define ACC64_STR1 \
    "{%0, %1, %2, %3, %4, %5, %6, %7, %8, %9, %10, %11, %12, %13, %14, %15, " \
    "%16, %17, %18, %19, %20, %21, %22, %23, %24, %25, %26, %27, %28, %29, %30, %31, " \
    "%32, %33, %34, %35, %36, %37, %38, %39, %40, %41, %42, %43, %44, %45, %46, %47, " \
    "%48, %49, %50, %51, %52, %53, %54, %55, %56, %57, %58, %59, %60, %61, %62, %63, "
DEVINL void wgmma_ss256(float (&d)[64], float (&e)[64], uint64_t da, uint64_t db, int scale_d) {
    asm volatile("{\n.reg .pred p;\nsetp.ne.b32 p, %130, 0;\n"
                 "wgmma.mma_async.sync.aligned.m64n256k16.f32.bf16.bf16 " ACC64_STR1 ACC64_STR2 ", %128, %129, p, 1, 1, 0, 1;\n}\n"
                 : ACC64(d), ACC64(e) : "l"(da), "l"(db), "r"(scale_d));
}

DEVINL void fence_regs(float (&d)[64]) {
#pragma unroll
    for (int i = 0; i < 64; i++) asm volatile("" : "+f"(d[i]) :: "memory");
}
DEVINL void fresh_regs(float (&d)[64]) {
#pragma unroll
    for (int i = 0; i < 64; i++) asm volatile("" : "=f"(d[i]));
}
DEVINL void fence_regs_u(uint32_t (&d)[32]) {
#pragma unroll
    for (int i = 0; i < 32; i++) asm volatile("" : "+r"(d[i]) :: "memory");
}

__global__ void __launch_bounds__(256) ln_kernel(const __nv_bfloat16* __restrict__ x) {
    if (threadIdx.x == 0) GT_MIN(0);
    asm volatile("griddepcontrol.launch_dependents;");
    const int warp = threadIdx.x >> 5, lane = threadIdx.x & 31;
    const int row = blockIdx.x * 8 + warp;
    {
        float4 z = make_float4(0.f, 0.f, 0.f, 0.f);
        float4* a = reinterpret_cast<float4*>(g_sacc) + (size_t)blockIdx.x * 1024;
#pragma unroll
        for (int i = 0; i < 4; i++) a[i * 256 + threadIdx.x] = z;
        if (blockIdx.x == 0 && threadIdx.x < 16) { g_cnt[threadIdx.x] = 0; g_done[threadIdx.x * 32] = 0; }
        if (blockIdx.x == 1 && threadIdx.x < 128) g_pflag[threadIdx.x] = 0;
    }
    const uint4* xr = reinterpret_cast<const uint4*>(x + (size_t)row * DM);
    uint4 v[2];
    v[0] = xr[lane]; v[1] = xr[lane + 32];
    float f[16];
#pragma unroll
    for (int i = 0; i < 2; i++) {
        const __nv_bfloat162* h = reinterpret_cast<const __nv_bfloat162*>(&v[i]);
#pragma unroll
        for (int j = 0; j < 4; j++) { float2 t = __bfloat1622float2(h[j]); f[i * 8 + 2 * j] = t.x; f[i * 8 + 2 * j + 1] = t.y; }
    }
    float s = 0.f;
#pragma unroll
    for (int i = 0; i < 16; i++) s += f[i];
#pragma unroll
    for (int o = 16; o > 0; o >>= 1) s += __shfl_xor_sync(0xffffffffu, s, o);
    const float mean = s * (1.0f / DM);
    float q = 0.f;
#pragma unroll
    for (int i = 0; i < 16; i++) { float d = f[i] - mean; q += d * d; }
#pragma unroll
    for (int o = 16; o > 0; o >>= 1) q += __shfl_xor_sync(0xffffffffu, q, o);
    const float mb = bf16_round(mean);
    const float vb = bf16_round(q * (1.0f / DM));
    const float den = bf16_round(sqrtf(bf16_round(vb + 1e-5f)));
    uint4 o4[2];
#pragma unroll
    for (int i = 0; i < 2; i++) {
        uint32_t* w = reinterpret_cast<uint32_t*>(&o4[i]);
#pragma unroll
        for (int j = 0; j < 4; j++) {
            float a = bf16_round(f[i * 8 + 2 * j] - mb) / den;
            float b = bf16_round(f[i * 8 + 2 * j + 1] - mb) / den;
            w[j] = pack_bf16(a, b);
        }
    }
    uint4* orow = reinterpret_cast<uint4*>(g_xn + (size_t)row * DM);
    orow[lane] = o4[0]; orow[lane + 32] = o4[1];
    if (threadIdx.x == 0) GT_MAX(1);
}

struct Unit { int type; int idx; int qpair; };
DEVINL int num_units(int cl) { return cl < 64 ? 2 : 20; }
DEVINL Unit get_unit(int cl, int i) {
    Unit u;
    if (cl < 32) {
        if (i == 0) { u.type = 0; u.idx = (cl >> 3) * 2; u.qpair = cl & 7; }
        else        { u.type = 1; u.idx = cl >> 3; u.qpair = cl & 7; }
    } else if (cl < 64) {
        if (i == 0) { u.type = 1; u.idx = cl >> 3; u.qpair = cl & 7; }
        else        { u.type = 2; u.idx = ((cl >> 3) + 3) & 3; u.qpair = cl & 7; }
    } else {
        if (i < 12) { int f = (cl - 64) * 12 + i; u.type = 0; u.idx = 8 + (f >> 3) * 2; u.qpair = f & 7; }
        else        { u.type = 3; u.idx = (cl - 64) * 2; u.qpair = i - 12; }
    }
    return u;
}

struct __align__(64) Params {
    CUtensorMap xn, wq, w1, k, v, wo, w2, h, h_st, out, acc, x;
};

__global__ void __cluster_dims__(CLUSTER, 1, 1) __launch_bounds__(NTHREADS, 1)
mega_kernel(const __grid_constant__ Params prm) {
    extern __shared__ uint8_t smem_raw[];
    const uint32_t smem_base = (smem_u32(smem_raw) + 1023u) & ~1023u;
    const uint32_t stash_base = smem_base + NSLOT * SLOT_BYTES;
    const uint32_t bar_base = stash_base + NSTASH * SLOT_BYTES;
    auto full_bar = [&](uint32_t s) { return bar_base + s * 8; };
    auto empty_bar = [&](uint32_t s) { return bar_base + (MAXSLOT + s) * 8; };

    const int tid = threadIdx.x;
    if (tid == 0) GT_MIN(2);
    const int wg = tid >> 7;
    const uint32_t rank = cluster_ctarank();
    const int pcl = blockIdx.x / CLUSTER;
    const int cl = pcl < 64 ? (pcl >> 1) + (pcl & 1) * 32 : pcl;
    const uint32_t slot0 = 0u, nslot0 = 6u;

    if (tid == 0) {
        s_limit = 1u << 20;
        for (int s = 0; s < MAXSLOT; s++) { mbar_init(full_bar(s), 1); mbar_init(empty_bar(s), 8 * CLUSTER); }
        asm volatile("fence.mbarrier_init.release.cluster;" ::: "memory");
    }
    __syncthreads();
    cluster_sync_all();

    const int nunits = num_units(cl);

    if (wg == 0) {
        asm volatile("setmaxnreg.dec.sync.aligned.u32 24;");
        if (tid == 0) {
            prefetch_tmap(&prm.xn); prefetch_tmap(&prm.wq); prefetch_tmap(&prm.w1); prefetch_tmap(&prm.k);
            prefetch_tmap(&prm.v); prefetch_tmap(&prm.wo); prefetch_tmap(&prm.w2); prefetch_tmap(&prm.h); prefetch_tmap(&prm.h_st);
            asm volatile("griddepcontrol.wait;" ::: "memory");
            GT_MAX(3);
            uint32_t slot = slot0, pbits = 0, cur_n = nslot0, skip = 7;
            auto acquire = [&]() -> uint32_t {
                mbar_wait(empty_bar(slot), ((pbits >> slot) & 1) ^ 1);
                mbar_expect_tx(full_bar(slot), SLOT_BYTES);
                return smem_base + slot * SLOT_BYTES;
            };
            auto advance = [&]() { pbits ^= 1u << slot; if (++slot == cur_n) slot = 0; if (slot == skip) slot++; };
            auto load_tile128 = [&](const CUtensorMap* tm, int row0, int col0) {
                uint32_t dst = acquire();
                uint32_t fb = full_bar(slot);
                tma_load_2d_mc(dst + rank * 8192, tm, col0, row0 + rank * 64, fb, (uint16_t)3);
                tma_load_2d_mc(dst + 16384 + rank * 8192, tm, col0 + 64, row0 + rank * 64, fb, (uint16_t)3);
                advance();
            };
            auto load_proj = [&](const CUtensorMap* ta, const CUtensorMap* tb, int arow, int bcol, int nk, int c0 = 0) {
#pragma unroll 1
                for (int c = c0; c < nk; c++) {
                    uint32_t dst = acquire();
                    uint32_t fb = full_bar(slot);
                    tma_load_2d(dst, ta, c * 64, arow, fb);
                    tma_load_2d_mc(dst + 16384 + rank * 8192, tb, bcol + rank * 64, c * 64, fb, (uint16_t)3);
                    advance();
                }
            };
            auto load_du = [&](const CUtensorMap* ta, const CUtensorMap* tb, int arow, int bcol, int nk = 8) {
#pragma unroll 1
                for (int c = 0; c < nk; c++) {
                    if ((c & 1) == 0) {
                        uint32_t dst = acquire();
                        tma_load_2d(dst, ta, c * 64, arow, full_bar(slot));
                        tma_load_2d(dst + 16384, ta, c * 64 + 64, arow, full_bar(slot));
                        advance();
                    }
                    uint32_t dst = acquire() + rank * 16384;
                    tma_load_2d_mc(dst, tb, bcol, c * 64, full_bar(slot), (uint16_t)3);
                    tma_load_2d_mc(dst + 8192, tb, bcol + 64, c * 64, full_bar(slot), (uint16_t)3);
                    advance();
                }
            };
#pragma unroll 1
            for (int ui = 0; ui < nunits; ui++) {
                const Unit u = get_unit(cl, ui);
                const int qt = u.qpair * 2 + rank;
                if (u.type == 1) {
                    load_du(&prm.xn, &prm.wq, qt * 128, u.idx * 512 + rank * 128);
                    load_du(&prm.xn, &prm.wq, qt * 128, u.idx * 512 + 256 + rank * 128);
                    cur_n = NSLOT;
                    {
                        const int r0 = u.idx * 4 * SEQ;
                        load_tile128(&prm.k, r0, 0);
#pragma unroll 1
                        for (int n = 1; n < 64; n++) {
                            load_tile128(&prm.k, r0 + n * 128, 0);
                            load_tile128(&prm.v, r0 + (n - 1) * 128, 0);
                        }
                        load_tile128(&prm.v, r0 + 63 * 128, 0);
                    }
                    cur_n = NSLOT + 2; skip = NSLOT - 1;
                    prefetch_tmap(&prm.acc);
#pragma unroll 1
                    for (int c = 0; c < 16; c++) {
                        const int row = (u.idx * 4 + 3 - (c & 1) * 2) * 128 + rank * 64;
                        const int col = (((c >> 2) + u.idx) & 3) * 128 + (c & 2) * 32;
                        uint32_t dst = acquire() + rank * 8192;
                        tma_load_2d_mc(dst, &prm.wo, col, row, full_bar(slot), (uint16_t)3);
                        tma_load_2d_mc(dst + 16384, &prm.wo, col, row - 128, full_bar(slot), (uint16_t)3);
                        advance();
                    }
                    cur_n = 6; skip = 7;
                } else if (u.type == 0) {
                    load_du(&prm.xn, &prm.w1, qt * 128, u.idx * 128 + rank * 128);
                } else if (u.type == 3) {
                    uint32_t n = 0, v;
                    do {
                        asm volatile("ld.acquire.gpu.global.u32 %0, [%1];" : "=r"(v) : "l"(&g_cnt[qt]) : "memory");
                    } while ((v >> 16) < 8u && ++n < (1u << 22));
                    asm volatile("fence.proxy.async;" ::: "memory");
                    load_du(&prm.h, &prm.w2, qt * 128, ((u.idx + 3 + rank) & 3) * 128, u.qpair == 0 ? 8 : KP);
                } else {
                    uint32_t n = 0, v;
                    do {
                        asm volatile("ld.acquire.gpu.global.u32 %0, [%1];" : "=r"(v) : "l"(&g_cnt[qt]) : "memory");
                    } while ((v & 0xffffu) < 28u && ++n < (1u << 22));
                    asm volatile("fence.proxy.async;" ::: "memory");
                    prefetch_tmap(&prm.out); prefetch_tmap(&prm.x);
                    load_proj(&prm.h, &prm.w2, qt * 128, u.idx * 128, 28, u.qpair == 0 ? 8 : KP);
                    {
                        uint32_t dst = acquire();
                        tma_load_2d(dst, &prm.x, u.idx * 128, qt * 128, full_bar(slot));
                        tma_load_2d(dst + 16384, &prm.x, u.idx * 128 + 64, qt * 128, full_bar(slot));
                        advance();
                    }
                    n = 0;
                    do {
                        asm volatile("ld.acquire.gpu.global.u32 %0, [%1];" : "=r"(v) : "l"(&g_done[qt * 32]) : "memory");
                    } while (v < 16u && ++n < (1u << 22));
                    asm volatile("fence.proxy.async;" ::: "memory");
#pragma unroll 1
                    for (int hf = 0; hf < 2; hf++) {
                        uint32_t dst = acquire();
#pragma unroll 1
                        for (int b = 0; b < 4; b++)
                            tma_load_2d(dst + b * 8192, &prm.acc, u.idx * 128 + b * 32, qt * 128 + hf * 64, full_bar(slot));
                        advance();
                    }
                }
            }
        }
        if ((cl < 32 || cl >= 64) && (tid >> 5) >= 1 && (tid >> 5) <= 2) {
            const int w = (tid >> 5) - 1;
            const int nf = cl < 32 ? 4 : 48;
#pragma unroll 1
            for (int g = 0; g < nf; g++) {
                const Unit u = get_unit(cl, g >> 2);
                const int qt = u.qpair * 2 + rank;
                named_sync(6 + (g & 1) * 4 + w, 160);
                if ((tid & 31) == 0) {
                    const uint32_t stg = stash_base + 2 * SLOT_BYTES + (g & 1) * 16384 + w * 8192;
                    asm volatile("fence.proxy.async.shared::cta;" ::: "memory");
                    tma_store_2d(&prm.h_st, u.idx * 128 + (g & 3) * 64, qt * 128 + w * 64, stg);
                    asm volatile("cp.async.bulk.commit_group;" ::: "memory");
                    asm volatile("cp.async.bulk.wait_group.read 0;" ::: "memory");
                }
                __syncwarp();
                if (g < 46) named_arrive(8 + (g & 1) * 4 + w, 160);
                if ((tid & 31) == 0 && (g & 1)) {
                    asm volatile("cp.async.bulk.wait_group 0;" ::: "memory");
                    asm volatile("fence.proxy.async;" ::: "memory");
                    asm volatile("red.release.gpu.global.add.u32 [%0], %1;" :: "l"(&g_cnt[qt]), "r"(u.idx < 4 ? 0x10001 : 1) : "memory");
                }
                __syncwarp();
            }
            if (cl >= 64) {
#pragma unroll 1
                for (int i = 0; i < 8; i++) {
                    named_sync(14 + w, 160);
                    if ((tid & 31) < 2)
                        asm volatile("red.release.gpu.global.add.u32 [%0], %1;" :: "l"(&g_pflag[(((cl - 64) * 16 + (tid & 31) * 8 + i) * 2 + rank) * 2 + w]), "r"(1) : "memory");
                    __syncwarp();
                }
            }
        }
        if (cl < 64 && (tid >> 5) >= 1 && (tid >> 5) <= 2) {
            const int w = (tid >> 5) - 1;
            const int orow = ((cl & 7) * 2 + rank) * 128 + w * 64;
            const int nr = cl < 32 ? 8 : 6;
#pragma unroll 1
            for (int r = 0; r < nr; r++) {
                named_sync(6 + (r & 1) * 4 + w, 160);
                if ((tid & 31) == 0) {
                    const uint32_t b0 = smem_base + ((r & 1) ? NSLOT + 2 : NSLOT - 1) * SLOT_BYTES + w * 16384;
                    const uint32_t b1 = b0 + 8192;
                    const int col = (((r >> 1) + (cl >> 3)) & 3) * 128 + (r & 1) * 64;
                    asm volatile("fence.proxy.async.shared::cta;" ::: "memory");
                    tma_red_add_2d(&prm.acc, col, orow, b0);
                    tma_red_add_2d(&prm.acc, col + 32, orow, b1);
                    asm volatile("cp.async.bulk.commit_group;" ::: "memory");
                    if (r < nr - (cl < 32 ? 2 : 1)) asm volatile("cp.async.bulk.wait_group.read 0;" ::: "memory");
                }
                __syncwarp();
                if (r < nr - (cl < 32 ? 2 : 1)) named_arrive(8 + (r & 1) * 4 + w, 160);
            }
            if ((tid & 31) == 0) {
                asm volatile("cp.async.bulk.wait_group 0;" ::: "memory");
                asm volatile("fence.proxy.async;" ::: "memory");
                asm volatile("red.release.gpu.global.add.u32 [%0], %1;" :: "l"(&g_done[((cl & 7) * 2 + rank) * 32]), "r"(1) : "memory");
            }
        }
        if (cl >= 32 && cl < 64 && (tid >> 5) == 3) {
            if ((tid & 31) < 2) {
                uint32_t n = 0, v;
                while (true) {
                    asm volatile("ld.acquire.gpu.global.u32 %0, [%1];" : "=r"(v) : "l"(&g_pflag[((cl - 32) * 2 + rank) * 2 + (tid & 31)]) : "memory");
                    if (v >= 1u || ++n > (1u << 16)) break;
                    __nanosleep(PSLEEP);
                }
            }
            __syncwarp();
            named_arrive(14, 160);
            named_arrive(15, 160);
        }
        __syncwarp();
        cluster_sync_all();
    } else {
        asm volatile("setmaxnreg.inc.sync.aligned.u32 240;");
        const int w = wg - 1;
        const int wu = __shfl_sync(0xffffffffu, w, 0);
        const int lane = tid & 31;
        const int wq = (tid >> 5) & 3;
        const int BAR_SELF = 1 + w, BAR_OTHER = 1 + (w ^ 1), BAR_WG = 3 + w;

        uint32_t slot = slot0, pbits = 0, cur_n = nslot0;
        auto advance = [&]() { pbits ^= 1u << slot; if (++slot == cur_n) slot = 0; };
        auto wait_full = [&]() { mbar_wait(full_bar(slot), (pbits >> slot) & 1); };
        auto release = [&](uint32_t s) {
            if (lane == 0) { mbar_arrive_cluster(empty_bar(s), 0); mbar_arrive_cluster(empty_bar(s), 1); }
        };

        float O[64], S[64];
        uint32_t A[32], P[32];
        const float cexp = 0.08838834764831845f * 1.4426950408889634f;

        if (w == 1) named_arrive(1, 256);
        TS();

        float4 T[16];
        auto proj_in = [&](int nk, int cld) {
            uint32_t prev = 0;
#pragma unroll
            for (int i = 0; i < 64; i++) S[i] = 0.f;
#pragma unroll 1
            for (int c = 0; c < nk; c++) {
                wait_full();
                const uint32_t base = smem_base + slot * SLOT_BYTES;
                const uint64_t da = make_desc(base + w * 8192, 16, 1024);
                const uint64_t db = make_desc(base + 16384, 8192, 1024);
                wg_fence();
#pragma unroll
                for (int kk = 0; kk < 4; kk++)
                    wgmma_ss<1>(S, da + kk * 2, db + kk * 128, (c | kk) != 0);
                wg_commit();
                if (c > 0) { wg_wait<1>(); release(prev); }
                prev = slot;
                advance();
                if (c == cld) {
                    named_sync(14 + w, 160);
                    const float4* pp = g_part + (size_t)(((cl - 32) * 2 + rank) * 2 + w) * 2048 + (tid & 127);
#pragma unroll
                    for (int i = 0; i < 16; i++) T[i] = __ldcg(pp + i * 128);
                }
            }
            wg_wait<0>();
            fence_regs(S);
            release(prev);
        };

        auto stage_out = [&](float (&D)[64], int half, uint32_t b0, uint32_t b1, bool wait_prev, int bar) {
            if (wait_prev) named_sync(bar + 2 + w, 160);
            const uint32_t ro = (uint32_t)(wq * 16 + (lane >> 2)) * 128 + (lane & 1) * 8;
            const uint32_t sw = (uint32_t)(lane >> 2);
#pragma unroll
            for (int jj = 0; jj < 8; jj++) {
                const int j = half * 8 + jj;
                const uint32_t a = ((jj >> 2) ? b1 : b0) + ro + (((uint32_t)((jj & 3) * 2 + ((lane & 3) >> 1)) ^ sw) << 4);
                asm volatile("st.shared.v2.f32 [%0], {%1, %2};" :: "r"(a), "f"(D[4 * j]), "f"(D[4 * j + 1]) : "memory");
                asm volatile("st.shared.v2.f32 [%0], {%1, %2};" :: "r"(a + 1024), "f"(D[4 * j + 2]), "f"(D[4 * j + 3]) : "memory");
            }
            named_arrive(bar + w, 160);
        };

        {
            const uint32_t sw = (uint32_t)(lane >> 2);
            const uint32_t rb = stash_base + 2 * SLOT_BYTES + (w * 64 + wq * 16 + (lane >> 2)) * 128 + (lane & 3) * 4;
            const int nsteps = cl < 32 ? 3 : (cl < 64 ? 2 : 13);
#pragma unroll 1
            for (int t = 0; ; t++) {
                uint32_t prev = 0, aslot = 0, preva = 0;
                const bool epi = cl < 32 ? t == 1 : (cl >= 64 && t > 0);
                const bool hold = cl < 64 && t == nsteps - 1;
                fresh_regs(S); fresh_regs(O);
#pragma unroll
                for (int c = 0; c < 8; c++) {
                    if ((c & 1) == 0) { wait_full(); preva = aslot; aslot = slot; advance(); }
                    wait_full();
                    const uint64_t da = make_desc(smem_base + aslot * SLOT_BYTES + (c & 1) * 16384 + wu * 8192, 16, 1024);
                    const uint64_t db = make_desc(smem_base + slot * SLOT_BYTES, 8192, 1024);
                    wg_fence();
#pragma unroll
                    for (int kk = 0; kk < 4; kk++)
                        wgmma_ss256(S, O, da + kk * 2, db + kk * 128, (c | kk) != 0);
                    wg_commit();
                    if (c > 0) { wg_wait<1>(); if (!(c == 7 && hold)) release(prev); if ((c & 1) == 0) release(preva); }
                    prev = slot;
                    advance();
                    if (epi) {
                        if ((c & 1) == 0) named_sync_if(c >= 4 || t > 1, 8 + ((c >> 1) & 1) * 4 + w, 160);
#pragma unroll
                        for (int j = 4 * (c & 3); j < 4 * (c & 3) + 4; j++) {
                            const uint32_t a = rb + (j >> 3) * 16384 + (((uint32_t)(j & 7) ^ sw) << 4);
                            asm volatile("st.shared.b32 [%0], %1;" :: "r"(a), "r"(silu_packed(c < 4 ? A[2 * j] : P[2 * j])) : "memory");
                            asm volatile("st.shared.b32 [%0], %1;" :: "r"(a + 1024), "r"(silu_packed(c < 4 ? A[2 * j + 1] : P[2 * j + 1])) : "memory");
                        }
                        if (c & 1) named_arrive(6 + ((c >> 1) & 1) * 4 + w, 160);
                    }
                }
                wg_wait<0>();
                fence_regs(S);
                fence_regs(O);
                if (!hold) release(prev);
                release(aslot);
                TS();
                if (t == nsteps - 1) break;
#pragma unroll
                for (int i = 0; i < 32; i++) { A[i] = pack_bf16(S[2 * i], S[2 * i + 1]); P[i] = pack_bf16(O[2 * i], O[2 * i + 1]); }
            }
        }
        if (cl >= 64) {
            float4* pp = g_part + (size_t)(((cl - 64) * 32 + rank) * 2 + w) * 2048 + (tid & 127);
#pragma unroll 1
            for (int i = 1; i < 8; i++) {
#pragma unroll
                for (int j = 0; j < 16; j++)
                    __stcg(pp + j * 128, make_float4(S[4 * j], S[4 * j + 1], S[4 * j + 2], S[4 * j + 3]));
#pragma unroll
                for (int j = 0; j < 32; j++) { A[j] = __float_as_uint(O[j]); P[j] = __float_as_uint(O[32 + j]); }
                fence_regs_u(A); fence_regs_u(P);
                uint32_t prev = 0, aslot = 0, preva = 0;
                fresh_regs(S); fresh_regs(O);
#pragma unroll
                for (int c = 0; c < KP; c++) {
                    if ((c & 1) == 0) { wait_full(); preva = aslot; aslot = slot; advance(); }
                    wait_full();
                    const uint64_t da = make_desc(smem_base + aslot * SLOT_BYTES + (c & 1) * 16384 + wu * 8192, 16, 1024);
                    const uint64_t db = make_desc(smem_base + slot * SLOT_BYTES, 8192, 1024);
                    wg_fence();
#pragma unroll
                    for (int kk = 0; kk < 4; kk++)
                        wgmma_ss256(S, O, da + kk * 2, db + kk * 128, (c | kk) != 0);
                    wg_commit();
                    if (c > 0) { wg_wait<1>(); release(prev); if ((c & 1) == 0) release(preva); }
                    prev = slot;
                    advance();
#pragma unroll
                    for (int j = c * 16 / KP; j < (c + 1) * 16 / KP; j++) {
                        const uint32_t* q = j < 8 ? &A[4 * j] : &P[4 * j - 32];
                        __stcg(pp + 32 * 2048 + j * 128, make_float4(__uint_as_float(q[0]), __uint_as_float(q[1]), __uint_as_float(q[2]), __uint_as_float(q[3])));
                    }
                }
                named_sync(14 + w, 160);
                pp += 4 * 2048;
                wg_wait<0>();
                fence_regs(S);
                fence_regs(O);
                release(prev);
                release(aslot);
                TS();
            }
#pragma unroll
            for (int j = 0; j < 16; j++)
                __stcg(pp + j * 128, make_float4(S[4 * j], S[4 * j + 1], S[4 * j + 2], S[4 * j + 3]));
#pragma unroll
            for (int j = 0; j < 16; j++)
                __stcg(pp + 32 * 2048 + j * 128, make_float4(O[4 * j], O[4 * j + 1], O[4 * j + 2], O[4 * j + 3]));
            named_sync(14 + w, 160);
            TS();
        }
        if (cl < 64) {
            const int qt = (cl & 7) * 2 + rank;
            slot = 0u; pbits = 0u;
            cur_n = NSLOT;
            const uint32_t qpark = stash_base + w * 8192 + (tid & 127) * 16;
            named_sync(5, 256);
            named_sync_if(cl < 32, 8 + w, 160);
            named_sync_if(cl < 32, 12 + w, 160);
#pragma unroll
            for (int i = 0; i < 8; i++) {
                const uint32_t a = qpark + (i >> 2) * 16384 + (i & 3) * 2048;
                asm volatile("st.shared.v4.b32 [%0], {%1, %2, %3, %4};" :: "r"(a + 2 * SLOT_BYTES),
                             "r"(P[4 * i]), "r"(P[4 * i + 1]), "r"(P[4 * i + 2]), "r"(P[4 * i + 3]) : "memory");
                asm volatile("st.shared.v4.b32 [%0], {%1, %2, %3, %4};" :: "r"(a + SLOT_BYTES),
                             "r"(pack_bf16(S[8 * i], S[8 * i + 1])), "r"(pack_bf16(S[8 * i + 2], S[8 * i + 3])),
                             "r"(pack_bf16(S[8 * i + 4], S[8 * i + 5])), "r"(pack_bf16(S[8 * i + 6], S[8 * i + 7])) : "memory");
                asm volatile("st.shared.v4.b32 [%0], {%1, %2, %3, %4};" :: "r"(a),
                             "r"(pack_bf16(O[8 * i], O[8 * i + 1])), "r"(pack_bf16(O[8 * i + 2], O[8 * i + 3])),
                             "r"(pack_bf16(O[8 * i + 4], O[8 * i + 5])), "r"(pack_bf16(O[8 * i + 6], O[8 * i + 7])) : "memory");
            }
            TS();
            {
                {
                    fresh_regs(S); fresh_regs(O);
                    float m0 = -INFINITY, m1 = -INFINITY, l0 = 0.f, l1 = 0.f;
                    auto issue_qk = [&](uint32_t sl) {
                        const uint32_t base = smem_base + sl * SLOT_BYTES;
                        const uint64_t db = make_desc(base, 16, 1024);
#pragma unroll
                        for (int kk = 0; kk < 8; kk++)
                            wgmma_rs<0>(S, A[4 * kk], A[4 * kk + 1], A[4 * kk + 2], A[4 * kk + 3],
                                        db + (kk >> 2) * 1024 + (kk & 3) * 2, kk != 0);
                        wg_commit();
                    };
                    auto issue_pv = [&](uint32_t sl, int first) {
                        const uint32_t base = smem_base + sl * SLOT_BYTES;
                        const uint64_t db = make_desc(base, 16384, 1024);
#pragma unroll
                        for (int kk = 0; kk < 8; kk++)
                            wgmma_rs<1>(O, P[4 * kk], P[4 * kk + 1], P[4 * kk + 2], P[4 * kk + 3],
                                        db + kk * 128, (kk != 0) || !first);
                        wg_commit();
                    };
                    float sc0, sc1, tok;
                    auto softmax = [&]() {
                        int r0 = __vimax3_s32(__float_as_int(m0), __float_as_int(S[0]), __float_as_int(S[1]));
                        int r1 = __vimax3_s32(__float_as_int(m1), __float_as_int(S[2]), __float_as_int(S[3]));
                        int t0 = max(__float_as_int(S[4]), __float_as_int(S[5]));
                        int t1 = max(__float_as_int(S[6]), __float_as_int(S[7]));
#pragma unroll
                        for (int j = 2; j < 16; j += 2) {
                            r0 = __vimax3_s32(r0, __float_as_int(S[4 * j]), __float_as_int(S[4 * j + 1]));
                            r1 = __vimax3_s32(r1, __float_as_int(S[4 * j + 2]), __float_as_int(S[4 * j + 3]));
                            t0 = __vimax3_s32(t0, __float_as_int(S[4 * j + 4]), __float_as_int(S[4 * j + 5]));
                            t1 = __vimax3_s32(t1, __float_as_int(S[4 * j + 6]), __float_as_int(S[4 * j + 7]));
                        }
                        r0 = max(r0, t0); r1 = max(r1, t1);
                        r0 = max(r0, __shfl_xor_sync(0xffffffffu, r0, 1));
                        r1 = max(r1, __shfl_xor_sync(0xffffffffu, r1, 1));
                        r0 = max(r0, __shfl_xor_sync(0xffffffffu, r0, 2));
                        r1 = max(r1, __shfl_xor_sync(0xffffffffu, r1, 2));
                        float n0 = __int_as_float(r0), n1 = __int_as_float(r1);
                        if (__any_sync(0xffffffffu, (r0 | r1) < 0)) {
                            float a0 = fmaxf(S[0], S[1]), a1 = fmaxf(S[2], S[3]);
#pragma unroll
                            for (int j = 1; j < 16; j++) {
                                a0 = fmaxf(a0, fmaxf(S[4 * j], S[4 * j + 1]));
                                a1 = fmaxf(a1, fmaxf(S[4 * j + 2], S[4 * j + 3]));
                            }
                            a0 = fmaxf(a0, __shfl_xor_sync(0xffffffffu, a0, 1));
                            a1 = fmaxf(a1, __shfl_xor_sync(0xffffffffu, a1, 1));
                            a0 = fmaxf(a0, __shfl_xor_sync(0xffffffffu, a0, 2));
                            a1 = fmaxf(a1, __shfl_xor_sync(0xffffffffu, a1, 2));
                            n0 = fmaxf(m0, a0); n1 = fmaxf(m1, a1);
                        }
                        sc0 = ex2((m0 - n0) * cexp); sc1 = ex2((m1 - n1) * cexp);
                        m0 = n0; m1 = n1;
                        const float b0 = -n0 * cexp, b1 = -n1 * cexp;
                        const float c0 = fmaf(sc0, 0.f, b0), c1 = fmaf(sc1, 0.f, b1);
                        float s0 = 0.f, s1 = 0.f;
#pragma unroll
                        for (int j = 0; j < 16; j++) {
                            S[4 * j]     = ex2(fmaf(S[4 * j], cexp, j < ESPLIT ? b0 : c0));
                            S[4 * j + 1] = ex2(fmaf(S[4 * j + 1], cexp, j < ESPLIT ? b0 : c0));
                            S[4 * j + 2] = ex2(fmaf(S[4 * j + 2], cexp, j < ESPLIT ? b1 : c1));
                            S[4 * j + 3] = ex2(fmaf(S[4 * j + 3], cexp, j < ESPLIT ? b1 : c1));
                            s0 += S[4 * j] + S[4 * j + 1];
                            s1 += S[4 * j + 2] + S[4 * j + 3];
                            if (j == KTOK) tok = TOKV;
                        }
                        l0 = l0 * sc0 + s0; l1 = l1 * sc1 + s1;
                    };
                    auto make_p = [&]() {
#pragma unroll
                        for (int i = 0; i < 32; i++) P[i] = pack_bf16(S[2 * i], S[2 * i + 1]);
                    };

                    mbar_wait(full_bar(0), 0);
                    named_sync(BAR_SELF, 256);
                    wg_fence();
                    issue_qk(0);
                    named_arrive(BAR_OTHER, 256);
                    wg_wait<0>();
                    fence_regs(S);
                    release(0);
                    softmax();
                    make_p();
#pragma unroll 1
                    for (int hj = 0; ; hj++) {
#pragma unroll 1
                    for (int n = 1; n < 16; n++) {
                        const uint32_t ks = (2 * n - 1) & 3, vs = (2 * n) & 3;
                        mbar_wait(full_bar(ks), ((2 * n - 1) >> 2) & 1);
                        named_sync(BAR_SELF, 256);
                        wg_fence();
                        issue_qk(ks);
                        mbar_wait(full_bar(vs), (n >> 1) & 1);
                        issue_pv(vs, n == 1);
                        named_arrive(BAR_OTHER, 256);
                        wg_wait<1>();
                        fence_regs(S);
                        release(ks);
                        softmax();
                        asm volatile("{\n.reg .pred p;\nsetp.eq.f32 p, %0, 0fFF800000;\n@p mbarrier.arrive.shared::cta.b64 _, [%1];\n}\n" :: "f"(tok), "r"(full_bar(0)) : "memory");
                        wg_wait<0>();
                        fence_regs(O);
                        fence_regs_u(P);
                        release(vs);
#pragma unroll
                        for (int j = 0; j < 16; j++) {
                            O[4 * j] *= sc0; O[4 * j + 1] *= sc0; O[4 * j + 2] *= sc1; O[4 * j + 3] *= sc1;
                        }
                        make_p();
                    }
                    if (hj == 3) break;
#pragma unroll
                    for (int i = 0; i < 8; i++)
                        asm volatile("ld.shared.v4.b32 {%0, %1, %2, %3}, [%4];" : "=r"(A[4 * i]), "=r"(A[4 * i + 1]), "=r"(A[4 * i + 2]), "=r"(A[4 * i + 3])
                                     : "r"(qpark + (2 - hj) * SLOT_BYTES + (i >> 2) * 16384 + (i & 3) * 2048) : "memory");
                    mbar_wait(full_bar(3), 1);
                    named_sync(BAR_SELF, 256);
                    wg_fence();
                    issue_qk(3);
                    mbar_wait(full_bar(0), 0);
                    issue_pv(0, 0);
                    named_arrive(BAR_OTHER, 256);
                    l0 += __shfl_xor_sync(0xffffffffu, l0, 1); l1 += __shfl_xor_sync(0xffffffffu, l1, 1);
                    l0 += __shfl_xor_sync(0xffffffffu, l0, 2); l1 += __shfl_xor_sync(0xffffffffu, l1, 2);
                    const float j0 = 1.0f / l0, j1 = 1.0f / l1;
                    m0 = -INFINITY; m1 = -INFINITY; l0 = 0.f; l1 = 0.f;
                    wg_wait<1>();
                    fence_regs(S);
                    release(3);
                    softmax();
                    asm volatile("{\n.reg .pred p;\nsetp.eq.f32 p, %0, 0fFF800000;\n@p mbarrier.arrive.shared::cta.b64 _, [%1];\n}\n" :: "f"(tok), "r"(full_bar(0)) : "memory");
                    wg_wait<0>();
                    fence_regs(O);
                    fence_regs_u(P);
                    release(0);
#pragma unroll
                    for (int i = 0; i < 8; i++)
                        asm volatile("st.shared.v4.b32 [%0], {%1, %2, %3, %4};" :: "r"(qpark + (2 - hj) * SLOT_BYTES + (i >> 2) * 16384 + (i & 3) * 2048),
                                     "r"(pack_bf16(O[8 * i] * j0, O[8 * i + 1] * j0)), "r"(pack_bf16(O[8 * i + 2] * j1, O[8 * i + 3] * j1)),
                                     "r"(pack_bf16(O[8 * i + 4] * j0, O[8 * i + 5] * j0)), "r"(pack_bf16(O[8 * i + 6] * j1, O[8 * i + 7] * j1)) : "memory");
                    make_p();
                    TS();
                    }
                    mbar_wait(full_bar(3), 1);
                    wg_fence();
                    issue_pv(3, 0);
                    wg_wait<0>();
                    fence_regs(O);
                    fence_regs_u(P);
                    l0 += __shfl_xor_sync(0xffffffffu, l0, 1); l1 += __shfl_xor_sync(0xffffffffu, l1, 1);
                    l0 += __shfl_xor_sync(0xffffffffu, l0, 2); l1 += __shfl_xor_sync(0xffffffffu, l1, 2);
                    const float i0 = 1.0f / l0, i1 = 1.0f / l1;
#pragma unroll
                    for (int j = 0; j < 16; j++) {
                        P[2 * j]     = pack_bf16(O[4 * j] * i0, O[4 * j + 1] * i0);
                        P[2 * j + 1] = pack_bf16(O[4 * j + 2] * i1, O[4 * j + 3] * i1);
                    }
                    TS();
                }
#pragma unroll
                for (int i = 0; i < 8; i++)
                    asm volatile("ld.shared.v4.b32 {%0, %1, %2, %3}, [%4];" : "=r"(A[4 * i]), "=r"(A[4 * i + 1]), "=r"(A[4 * i + 2]), "=r"(A[4 * i + 3])
                                 : "r"(qpark + (i >> 2) * 16384 + (i & 3) * 2048) : "memory");
                uint32_t B[32], C[32];
#pragma unroll
                for (int i = 0; i < 8; i++) {
                    asm volatile("ld.shared.v4.b32 {%0, %1, %2, %3}, [%4];" : "=r"(B[4 * i]), "=r"(B[4 * i + 1]), "=r"(B[4 * i + 2]), "=r"(B[4 * i + 3])
                                 : "r"(qpark + SLOT_BYTES + (i >> 2) * 16384 + (i & 3) * 2048) : "memory");
                    asm volatile("ld.shared.v4.b32 {%0, %1, %2, %3}, [%4];" : "=r"(C[4 * i]), "=r"(C[4 * i + 1]), "=r"(C[4 * i + 2]), "=r"(C[4 * i + 3])
                                 : "r"(qpark + 2 * SLOT_BYTES + (i >> 2) * 16384 + (i & 3) * 2048) : "memory");
                }
                named_arrive(BAR_WG, 256);
                uint32_t prev = 0;
                cur_n = 6;
                slot = blockIdx.y;
                fresh_regs(O);
                auto chunk = [&](auto half, int c) {
                    constexpr int H = decltype(half)::value;
#pragma unroll
                    for (int j = 0; j < 2; j++) {
                        wait_full();
                        const uint64_t db = make_desc(smem_base + slot * SLOT_BYTES, 16384, 1024);
                        wg_fence();
                        uint32_t (&a0)[32] = j == 0 ? P : B;
                        uint32_t (&a1)[32] = j == 0 ? A : C;
#pragma unroll
                        for (int kk = 0; kk < 8; kk++)
                            wgmma_rs64<H>(O, a0[4 * kk], a0[4 * kk + 1], a0[4 * kk + 2], a0[4 * kk + 3], db + kk * 128, (j | kk) != 0);
#pragma unroll
                        for (int kk = 0; kk < 8; kk++)
                            wgmma_rs64<H>(O, a1[4 * kk], a1[4 * kk + 1], a1[4 * kk + 2], a1[4 * kk + 3], db + 1024 + kk * 128, 1);
                        wg_commit();
                        if (c == 0) release(4 + j);
                        if (c > 0 || j > 0) { wg_wait<1>(); release(prev); }
                        prev = slot;
                        pbits ^= 1u << slot; if (++slot == cur_n) slot = 0; if (slot == NSLOT - 1) slot++;
                        if (c > 0 && j == 0) {
                            fence_half<H ^ 1>(O);
                            if (c == 1) named_sync(3 + (w ^ 1), 256);
                            const uint32_t sb = smem_base + (H ? NSLOT - 1 : NSLOT + 2) * SLOT_BYTES + w * 16384;
                            if (c < 7 || cl < 32) stage_out(O, H ^ 1, sb, sb + 8192, c > 2, H ? 6 : 10);
                            else { named_sync(8 + w, 160); release(NSLOT - 1); }
                        }
                    }
                };
                using H0 = std::integral_constant<int, 0>; using H1 = std::integral_constant<int, 1>;
                chunk(H0{}, 0); chunk(H1{}, 1); chunk(H0{}, 2); chunk(H1{}, 3); chunk(H0{}, 4); chunk(H1{}, 5); chunk(H0{}, 6); chunk(H1{}, 7);
                wg_wait<0>(); fence_regs(O); release(prev);
                fence_regs_u(P); fence_regs_u(A); fence_regs_u(B); fence_regs_u(C);
                fresh_regs(S);
                cur_n = 6;
                if (cl < 32) stage_out(O, 1, stash_base + 2 * SLOT_BYTES + w * 16384, stash_base + 2 * SLOT_BYTES + w * 16384 + 8192, true, 10);
                TS();
            }
            {
                const int cidx = ((cl >> 3) + 3) & 3;
                const bool real = cl >= 32;
#pragma unroll
                for (int i = 0; i < 16; i++) asm volatile("" : "=f"(T[i].x), "=f"(T[i].y), "=f"(T[i].z), "=f"(T[i].w));
                { const int kp = (cl & 7) == 0 ? 8 : KP; if (real) proj_in(28 - kp, CLD - kp); }
                TS();
#pragma unroll
                for (int i = 0; i < 16; i++) {
                    A[2 * i]     = silu_pair(S[4 * i] + T[i].x, S[4 * i + 1] + T[i].y);
                    A[2 * i + 1] = silu_pair(S[4 * i + 2] + T[i].z, S[4 * i + 3] + T[i].w);
                }
                TS();
                const uint32_t xs = smem_base + slot * SLOT_BYTES;
                const uint32_t sw = (uint32_t)(lane >> 2);
                const uint32_t rb = xs + (w * 64 + wq * 16 + (lane >> 2)) * 128 + (lane & 3) * 4;
                if (real) wait_full();
                advance();
#pragma unroll
                for (int i = 0; i < 32; i++) {
                    const int j = i >> 1;
                    const uint32_t a = rb + (j >> 3) * 16384 + (((uint32_t)(j & 7) ^ sw) << 4) + (i & 1) * 1024;
                    asm volatile("ld.shared.b32 %0, [%1];" : "=r"(P[i]) : "r"(a) : "memory");
                }
                if (wu == 1) advance();
                const uint32_t ro = smem_base + slot * SLOT_BYTES + (uint32_t)(wq * 16 + (lane >> 2)) * 128 + (lane & 1) * 8;
                if (real) wait_full();
#pragma unroll
                for (int i = 0; i < 32; i++) {
                    const int j = i >> 1;
                    const uint32_t b = ro + (j >> 2) * 8192 + (((uint32_t)((j & 3) * 2 + ((lane & 3) >> 1)) ^ sw) << 4) + (i & 1) * 1024;
                    asm volatile("ld.shared.v2.f32 {%0, %1}, [%2];" : "=f"(S[2 * i]), "=f"(S[2 * i + 1]) : "r"(b) : "memory");
                }
#pragma unroll
                for (int i = 0; i < 32; i++) {
                    const int j = i >> 1;
                    const uint32_t a = rb + (j >> 3) * 16384 + (((uint32_t)(j & 7) ^ sw) << 4) + (i & 1) * 1024;
                    uint32_t pv;
                    asm("mul.rn.bf16x2 %0, %1, %2;" : "=r"(pv) : "r"(pack_bf16(S[2 * i] + O[2 * i], S[2 * i + 1] + O[2 * i + 1])), "r"(A[i]));
                    const float r0 = __uint_as_float(P[i] << 16) + __uint_as_float(pv << 16);
                    const float r1 = __uint_as_float(P[i] & 0xffff0000u) + __uint_as_float(pv & 0xffff0000u);
                    asm volatile("st.shared.b32 [%0], %1;" :: "r"(a), "r"(pack_bf16(r0, r1)) : "memory");
                }
                asm volatile("fence.proxy.async.shared::cta;" ::: "memory");
                named_sync(BAR_WG, 128);
                if ((tid & 127) == 0 && real) {
                    tma_store_2d(&prm.out, cidx * 128, qt * 128 + w * 64, xs + w * 8192);
                    tma_store_2d(&prm.out, cidx * 128 + 64, qt * 128 + w * 64, xs + 16384 + w * 8192);
                    asm volatile("cp.async.bulk.commit_group;" ::: "memory");
                    asm volatile("cp.async.bulk.wait_group.read 0;" ::: "memory");
                }
                TS();
            }
        }
        if ((tid & 127) == 0) { GT_MIN(4); GT_MAX(5); }
        cluster_sync_all();
    }
}

typedef CUresult (*PFN_encodeTiled)(CUtensorMap*, CUtensorMapDataType, cuuint32_t, void*, const cuuint64_t*,
                                    const cuuint64_t*, const cuuint32_t*, const cuuint32_t*, CUtensorMapInterleave,
                                    CUtensorMapSwizzle, CUtensorMapL2promotion, CUtensorMapFloatOOBfill);

static void make_tmap(PFN_encodeTiled enc, CUtensorMap* tm, const void* ptr, uint64_t rows, uint64_t cols,
                      uint32_t box_rows, uint32_t box_cols, bool f32 = false) {
    cuuint64_t gdim[2] = {cols, rows};
    cuuint64_t gstr[1] = {cols * (f32 ? 4 : 2)};
    cuuint32_t box[2] = {box_cols, box_rows};
    cuuint32_t estr[2] = {1, 1};
    enc(tm, f32 ? CU_TENSOR_MAP_DATA_TYPE_FLOAT32 : CU_TENSOR_MAP_DATA_TYPE_BFLOAT16, 2, const_cast<void*>(ptr), gdim, gstr, box, estr,
        CU_TENSOR_MAP_INTERLEAVE_NONE, CU_TENSOR_MAP_SWIZZLE_128B, CU_TENSOR_MAP_L2_PROMOTION_L2_256B,
        CU_TENSOR_MAP_FLOAT_OOB_FILL_NONE);
}

extern "C" void kernel_launch(void* const* d_in, const int* in_sizes, int n_in, void* d_out, int out_size) {
    const __nv_bfloat16* x  = (const __nv_bfloat16*)d_in[0];
    const void* kc = d_in[1];
    const void* vc = d_in[2];
    const void* wq = d_in[3];
    const void* wo = d_in[4];
    const void* w1 = d_in[6];
    const void* w2 = d_in[7];
    __nv_bfloat16* out = (__nv_bfloat16*)d_out;

    static PFN_encodeTiled enc = nullptr;
    static void* xn_ptr = nullptr;
    static void* h_ptr = nullptr;
    static void* acc_ptr = nullptr;
    if (!enc) {
        void* fn = nullptr;
        cudaDriverEntryPointQueryResult qres;
        cudaGetDriverEntryPoint("cuTensorMapEncodeTiled", &fn, cudaEnableDefault, &qres);
        enc = (PFN_encodeTiled)fn;
        cudaGetSymbolAddress(&xn_ptr, g_xn);
        cudaGetSymbolAddress(&h_ptr, g_h);
        cudaGetSymbolAddress(&acc_ptr, g_sacc);
        cudaFuncSetAttribute(mega_kernel, cudaFuncAttributeMaxDynamicSharedMemorySize, SMEM_BYTES);
    }
    Params prm;
    make_tmap(enc, &prm.xn, xn_ptr, SEQ, DM, 128, 64);
    make_tmap(enc, &prm.wq, wq, DM, NH * DH, 64, 64);
    make_tmap(enc, &prm.w1, w1, DM, FF, 64, 64);
    make_tmap(enc, &prm.k, kc, (uint64_t)NH * SEQ, DH, 64, 64);
    make_tmap(enc, &prm.v, vc, (uint64_t)NH * SEQ, DH, 64, 64);
    make_tmap(enc, &prm.wo, wo, NH * DH, DM, 64, 64);
    make_tmap(enc, &prm.w2, w2, FF, DM, 64, 64);
    make_tmap(enc, &prm.h, h_ptr, SEQ, FF, 128, 64);
    make_tmap(enc, &prm.h_st, h_ptr, SEQ, FF, 64, 64);
    make_tmap(enc, &prm.out, out, SEQ, DM, 64, 64);
    make_tmap(enc, &prm.x, x, SEQ, DM, 128, 64);
    make_tmap(enc, &prm.acc, acc_ptr, SEQ, DM, 64, 32, true);

    cudaStream_t st = cudaStreamPerThread;
    ln_kernel<<<SEQ / 8, 256, 0, st>>>(x);

    cudaLaunchAttribute attr[1];
    attr[0].id = cudaLaunchAttributeProgrammaticStreamSerialization;
    attr[0].val.programmaticStreamSerializationAllowed = 1;
    {
        cudaLaunchConfig_t cfg = {};
        cfg.gridDim = dim3(132); cfg.blockDim = dim3(NTHREADS); cfg.dynamicSmemBytes = SMEM_BYTES; cfg.stream = st;
        cfg.attrs = attr; cfg.numAttrs = 1;
        cudaLaunchKernelEx(&cfg, mega_kernel, prm);
    }
}
```
